```python
import torch

def _softmax(x, axis=-1):
    return torch.softmax(x, dim=axis)
def _gelu(x):
    return torch.nn.functional.gelu(x, approximate="tanh")
def _silu(x):
    return torch.nn.functional.silu(x)
def _sigmoid(x):
    return torch.sigmoid(x)
def _layernorm(x, axis=-1, eps=1e-5):
    m = x.mean(dim=axis, keepdim=True)
    v = x.var(dim=axis, keepdim=True, unbiased=False)
    return (x - m) / torch.sqrt(v + eps)
def _scatter_add(tgt, idx, src, axis=0):
    return tgt.clone().index_add_(axis, idx, src)
def _segment_sum(src, seg, n):
    out = torch.zeros((n,) + src.shape[1:], dtype=src.dtype)
    return out.index_add_(0, seg, src)
def _pad(x, pw):
    flat = tuple(v for pair in reversed(pw) for v in pair)
    return torch.nn.functional.pad(x, flat)

kernel_name = 'concat_heads__spectral_fnet__ssm_conv_h3__prompt'

def setup_inputs():

    _w = (lambda a: (lambda t: t.to(torch.bfloat16) if t.is_floating_point() else t)(torch.as_tensor(a)))
    def _A_setup():
        B, S, D = 1, 2048, 1024
        ns = torch.arange(S)[:, None] * torch.arange(S)[None, :]
        nd = torch.arange(D)[:, None] * torch.arange(D)[None, :]
        Ws_re = torch.cos(-2.0 * torch.pi * ns / S).to(float)
        Ws_im = torch.sin(-2.0 * torch.pi * ns / S).to(float)
        Wd_re = torch.cos(-2.0 * torch.pi * nd / D).to(float)
        Wd_im = torch.sin(-2.0 * torch.pi * nd / D).to(float)
        return {
            "x": _w((lambda *s: torch.randn(*s, dtype=torch.bfloat16) * 0.05)(B, S, D)),
            "dft_seq_re": _w(Ws_re),
            "dft_seq_im": _w(Ws_im),
            "dft_hid_re": _w(Wd_re),
            "dft_hid_im": _w(Wd_im),
        }
    _A_in = _A_setup()

    def _B_setup():
        B, S, D = 1, 2048, 1024
        ks = 4
        return {
            "q": _w((lambda *s: torch.randn(*s, dtype=torch.bfloat16) * 0.05)(B, S, D)),
            "k": _w((lambda *s: torch.randn(*s, dtype=torch.bfloat16) * 3.2)(B, S, D)),
            "v": _w((lambda *s: torch.randn(*s, dtype=torch.bfloat16) * 3.2)(B, S, D)),
            "shift_k": _w((lambda *s: torch.randn(*s, dtype=torch.bfloat16) * 3.2)(D, ks) * 0.5),
            "ssm_k": _w((lambda *s: torch.randn(*s, dtype=torch.bfloat16) * 3.2)(D, S) * (1.0 / S ** 0.5)),
            "ssm_D": _w((lambda *s: torch.randn(*s, dtype=torch.bfloat16) * 3.2)(D)),
        }
    _B_in = _B_setup()

    return {
        "A_x": _A_in["x"],
        "A_dft_seq_re": _A_in["dft_seq_re"],
        "A_dft_seq_im": _A_in["dft_seq_im"],
        "A_dft_hid_re": _A_in["dft_hid_re"],
        "A_dft_hid_im": _A_in["dft_hid_im"],
        "B_q": _B_in["q"],
        "B_k": _B_in["k"],
        "B_v": _B_in["v"],
        "B_shift_k": _B_in["shift_k"],
        "B_ssm_k": _B_in["ssm_k"],
        "B_ssm_D": _B_in["ssm_D"],
    }

def reference(A_x, A_dft_seq_re, A_dft_seq_im, A_dft_hid_re, A_dft_hid_im, B_q, B_k, B_v, B_shift_k, B_ssm_k, B_ssm_D):
    def _A_ref(x, dft_seq_re, dft_seq_im, dft_hid_re, dft_hid_im):
        a = torch.einsum("bsd,ed->bse", x, dft_hid_re)
        b = torch.einsum("bsd,ed->bse", x, dft_hid_im)
        y = torch.einsum("ts,bse->bte", dft_seq_re, a) - torch.einsum("ts,bse->bte", dft_seq_im, b)
        return y

    def _B_ref(q, k, v, shift_k, ssm_k, ssm_D):
        B, S, D = q.shape
        ks = shift_k.shape[-1]
        k_pad = _pad(k, ((0, 0), (ks - 1, 0), (0, 0)))
        k_shift = torch.zeros_like(k)
        for t in range(ks):
            k_shift = k_shift + k_pad[:, t:t + S, :] * shift_k[:, ks - 1 - t][None, None, :]
        kv = k_shift * v
        L = 2 * S
        kv_pad = _pad(kv, ((0, 0), (0, S), (0, 0)))
        kf_pad = _pad(ssm_k, ((0, 0), (0, S)))
        kv_f = (lambda x, axes=(-2,-1): torch.fft.rfft2(x.float(), dim=axes))(kv_pad[:, None, :, :], axes=(1, 2))
        kf_f = (lambda x, axes=(-2,-1): torch.fft.rfft2(x.float(), dim=axes))(kf_pad[:, None, :], axes=(1, 2))
        kf_f = (lambda x, *d: x.permute(*d))(kf_f, 1, 2, 0)
        y_f = kv_f * kf_f[None, :, :, :]
        y = (lambda x, s, axes=(-2,-1): torch.fft.irfft2(x, s=s, dim=axes).to(torch.bfloat16))(y_f, (1, L), axes=(1, 2))[:, 0, :S, :]
        y = y + kv * ssm_D[None, None, :]
        return q * y

    a = _A_ref(A_x, A_dft_seq_re, A_dft_seq_im, A_dft_hid_re, A_dft_hid_im)
    b = _B_ref(B_q, B_k, B_v, B_shift_k, B_ssm_k, B_ssm_D)
    return torch.concatenate([a, b], axis=-1)
```

```cpp
#include <cuda_runtime.h>
#include <cuda_bf16.h>
#include <cuda.h>
#include <stdint.h>

typedef __nv_bfloat16 bf16;

constexpr int S_LEN = 2048;
constexpr int D_DIM = 1024;

__device__ bf16 g_abT[2048 * 2048];
__device__ bf16 g_kv[2048 * 1024];

__device__ __forceinline__ uint32_t smem_u32(const void* p) {
    return (uint32_t)__cvta_generic_to_shared(p);
}
__device__ __forceinline__ void mbar_init(uint32_t bar, uint32_t count) {
    asm volatile("mbarrier.init.shared::cta.b64 [%0], %1;" ::"r"(bar), "r"(count) : "memory");
}
__device__ __forceinline__ void mbar_expect_tx(uint32_t bar, uint32_t bytes) {
    asm volatile("mbarrier.arrive.expect_tx.shared::cta.b64 _, [%0], %1;" ::"r"(bar), "r"(bytes) : "memory");
}
__device__ __forceinline__ void mbar_arrive_local(uint32_t bar) {
    asm volatile("mbarrier.arrive.shared::cta.b64 _, [%0];" ::"r"(bar) : "memory");
}
__device__ __forceinline__ void mbar_arrive_remote(uint32_t bar, uint32_t cta) {
    asm volatile(
        "{\n"
        ".reg .b32 ra;\n"
        "mapa.shared::cluster.u32 ra, %0, %1;\n"
        "mbarrier.arrive.release.cluster.shared::cluster.b64 _, [ra];\n"
        "}\n" ::"r"(bar), "r"(cta) : "memory");
}
__device__ __forceinline__ void mbar_wait(uint32_t bar, uint32_t parity) {
    asm volatile(
        "{\n"
        ".reg .pred p;\n"
        "WAIT_LOOP:\n"
        "mbarrier.try_wait.parity.shared::cta.b64 p, [%0], %1;\n"
        "@p bra WAIT_DONE;\n"
        "bra WAIT_LOOP;\n"
        "WAIT_DONE:\n"
        "}\n" ::"r"(bar), "r"(parity) : "memory");
}
__device__ __forceinline__ void tma_load_2d(uint32_t dst, const CUtensorMap* map, uint32_t bar, int c0, int c1) {
    asm volatile(
        "cp.async.bulk.tensor.2d.shared::cluster.global.mbarrier::complete_tx::bytes [%0], [%1, {%3, %4}], [%2];"
        ::"r"(dst), "l"(map), "r"(bar), "r"(c0), "r"(c1) : "memory");
}
__device__ __forceinline__ void tma_load_2d_mc(uint32_t dst, const CUtensorMap* map, uint32_t bar, int c0, int c1,
                                               uint16_t mask) {
    asm volatile(
        "cp.async.bulk.tensor.2d.shared::cluster.global.mbarrier::complete_tx::bytes.multicast::cluster [%0], [%1, {%3, %4}], [%2], %5;"
        ::"r"(dst), "l"(map), "r"(bar), "r"(c0), "r"(c1), "h"(mask) : "memory");
}
__device__ __forceinline__ uint32_t cluster_rank() {
    uint32_t r;
    asm volatile("mov.u32 %0, %%cluster_ctarank;" : "=r"(r));
    return r;
}
__device__ __forceinline__ void cluster_arrive() {
    asm volatile("barrier.cluster.arrive.release.aligned;" ::: "memory");
}
__device__ __forceinline__ void cluster_wait() {
    asm volatile("barrier.cluster.wait.acquire.aligned;" ::: "memory");
}
__device__ __forceinline__ void wgmma_fence() { asm volatile("wgmma.fence.sync.aligned;" ::: "memory"); }
__device__ __forceinline__ void wgmma_commit() { asm volatile("wgmma.commit_group.sync.aligned;" ::: "memory"); }
template <int N>
__device__ __forceinline__ void wgmma_wait() {
    asm volatile("wgmma.wait_group.sync.aligned %0;" ::"n"(N) : "memory");
}
__device__ __forceinline__ uint64_t make_desc_sw128(uint32_t saddr) {
    uint64_t d = 0;
    d |= (uint64_t)((saddr & 0x3FFFF) >> 4);
    d |= (uint64_t)1 << 16;
    d |= (uint64_t)(1024 >> 4) << 32;
    d |= (uint64_t)1 << 62;
    return d;
}

#define ACC8(b) "+f"(acc[b + 0]), "+f"(acc[b + 1]), "+f"(acc[b + 2]), "+f"(acc[b + 3]), "+f"(acc[b + 4]), "+f"(acc[b + 5]), "+f"(acc[b + 6]), "+f"(acc[b + 7])

__device__ __forceinline__ void wgmma_m64n256k16(float (&acc)[128], uint64_t da, uint64_t db) {
    asm volatile(
        "{\n"
        ".reg .pred p;\n"
        "setp.ne.b32 p, 1, 0;\n"
        "wgmma.mma_async.sync.aligned.m64n256k16.f32.bf16.bf16 "
        "{%0, %1, %2, %3, %4, %5, %6, %7, %8, %9, %10, %11, %12, %13, %14, %15, "
        "%16, %17, %18, %19, %20, %21, %22, %23, %24, %25, %26, %27, %28, %29, %30, %31, "
        "%32, %33, %34, %35, %36, %37, %38, %39, %40, %41, %42, %43, %44, %45, %46, %47, "
        "%48, %49, %50, %51, %52, %53, %54, %55, %56, %57, %58, %59, %60, %61, %62, %63, "
        "%64, %65, %66, %67, %68, %69, %70, %71, %72, %73, %74, %75, %76, %77, %78, %79, "
        "%80, %81, %82, %83, %84, %85, %86, %87, %88, %89, %90, %91, %92, %93, %94, %95, "
        "%96, %97, %98, %99, %100, %101, %102, %103, %104, %105, %106, %107, %108, %109, %110, %111, "
        "%112, %113, %114, %115, %116, %117, %118, %119, %120, %121, %122, %123, %124, %125, %126, %127}, "
        "%128, %129, p, 1, 1, 0, 0;\n"
        "}\n"
        : ACC8(0), ACC8(8), ACC8(16), ACC8(24), ACC8(32), ACC8(40), ACC8(48), ACC8(56), ACC8(64), ACC8(72), ACC8(80),
          ACC8(88), ACC8(96), ACC8(104), ACC8(112), ACC8(120)
        : "l"(da), "l"(db));
}

__device__ __forceinline__ uint32_t pack_bf16(float lo, float hi) {
    __nv_bfloat162 v = __floats2bfloat162_rn(lo, hi);
    return *reinterpret_cast<uint32_t*>(&v);
}
__device__ __forceinline__ float bf_lo(uint32_t v) { return __uint_as_float(v << 16); }
__device__ __forceinline__ float bf_hi(uint32_t v) { return __uint_as_float(v & 0xFFFF0000u); }

constexpr int G_STAGES = 4;
constexpr int G_A_BYTES = 128 * 64 * 2;
constexpr int G_B_BYTES = 256 * 64 * 2;
constexpr int G_STAGE_BYTES = G_A_BYTES + G_B_BYTES;
constexpr int G_XCHG_BYTES = 32768;
constexpr int G_SMEM_BYTES = G_STAGES * G_STAGE_BYTES + G_XCHG_BYTES + 1024 + 256;

template <int MODE>
__global__ void __launch_bounds__(384, 1)
gemm_kernel(const __grid_constant__ CUtensorMap mapA0, const __grid_constant__ CUtensorMap mapA1,
            const __grid_constant__ CUtensorMap mapB, bf16* __restrict__ out) {
    extern __shared__ uint8_t smem_raw[];
    uint32_t sbase = (smem_u32(smem_raw) + 1023) & ~1023u;
    uint8_t* sgen = smem_raw + (sbase - smem_u32(smem_raw));
    const uint32_t sA = sbase;
    const uint32_t sB = sbase + G_STAGES * G_A_BYTES;
    const uint32_t sX = sbase + G_STAGES * G_STAGE_BYTES;
    const uint32_t sBar = sX + G_XCHG_BYTES;
    auto full_bar = [&](int s) { return sBar + 8 * s; };
    auto empty_bar = [&](int s) { return sBar + 8 * (G_STAGES + s); };

    constexpr int KB = (MODE == 0) ? (D_DIM / 64) : (S_LEN / 64);
    const uint32_t crank = cluster_rank();
    const int prank = crank & 1;
    const int part = (MODE == 1) ? (crank >> 1) : 0;
    const int cid = (MODE == 0) ? (blockIdx.x >> 1) : (blockIdx.x >> 2);
    const int m_tile = (cid & 7) * 2 + prank;
    const int n_tile = cid >> 3;
    const int warp = threadIdx.x >> 5;
    const int lane = threadIdx.x & 31;

    if (threadIdx.x == 0) {
        for (int s = 0; s < G_STAGES; s++) {
            mbar_init(full_bar(s), 1);
            mbar_init(empty_bar(s), 4);
        }
        asm volatile("fence.mbarrier_init.release.cluster;" ::: "memory");
    }
    __syncthreads();
    cluster_arrive();
    cluster_wait();

    if (warp >= 8) {
        asm volatile("setmaxnreg.dec.sync.aligned.u32 40;");
        if (warp == 8 && lane == 0) {
            const CUtensorMap* mA;
            int a_row, b_row;
            if (MODE == 0) {
                mA = (m_tile < 8) ? &mapA0 : &mapA1;
                a_row = (m_tile & 7) * 128;
                b_row = n_tile * 256 + prank * 128;
            } else {
                mA = (part == 0) ? &mapA0 : &mapA1;
                a_row = m_tile * 128;
                b_row = part * 1024 + n_tile * 256 + prank * 128;
            }
            const uint16_t mask = (uint16_t)(3u << (part * 2));
            for (int kb = 0; kb < KB; kb++) {
                const int st = kb % G_STAGES;
                const uint32_t ph = (kb / G_STAGES) & 1;
                mbar_wait(empty_bar(st), ph ^ 1);
                mbar_expect_tx(full_bar(st), G_STAGE_BYTES);
                tma_load_2d(sA + st * G_A_BYTES, mA, full_bar(st), kb * 64, a_row);
                tma_load_2d_mc(sB + st * G_B_BYTES + prank * 16384, &mapB, full_bar(st), kb * 64, b_row, mask);
            }
        }
        if (MODE == 1) {
            cluster_arrive();
            cluster_wait();
        }
    } else {
        asm volatile("setmaxnreg.inc.sync.aligned.u32 232;");
        const int wg = warp >> 2;
        float acc[128];
#pragma unroll
        for (int i = 0; i < 128; i++) acc[i] = 0.f;
        for (int kb = 0; kb < KB; kb++) {
            const int st = kb % G_STAGES;
            const uint32_t ph = (kb / G_STAGES) & 1;
            mbar_wait(full_bar(st), ph);
            const uint64_t da = make_desc_sw128(sA + st * G_A_BYTES + wg * 8192);
            const uint64_t db = make_desc_sw128(sB + st * G_B_BYTES);
            wgmma_fence();
#pragma unroll
            for (int k = 0; k < 4; k++) wgmma_m64n256k16(acc, da + 2 * k, db + 2 * k);
            wgmma_commit();
            wgmma_wait<1>();
            if (kb > 0 && (threadIdx.x & 127) == 0) {
                const int pst = (kb - 1) % G_STAGES;
                mbar_arrive_remote(empty_bar(pst), part * 2 + 0);
                mbar_arrive_remote(empty_bar(pst), part * 2 + 1);
            }
        }
        wgmma_wait<0>();

        const int row0 = wg * 64 + (warp & 3) * 16 + (lane >> 2);
        const int colq = (lane & 3) * 2;
        if (MODE == 0) {
            bf16* dst = g_abT + (size_t)(m_tile * 128 + row0) * 2048 + n_tile * 256 + colq;
#pragma unroll
            for (int j = 0; j < 32; j++) {
                *reinterpret_cast<uint32_t*>(dst + j * 8) = pack_bf16(acc[4 * j], acc[4 * j + 1]);
                *reinterpret_cast<uint32_t*>(dst + 8 * 2048 + j * 8) = pack_bf16(acc[4 * j + 2], acc[4 * j + 3]);
            }
        } else {
            const int tid = threadIdx.x & 127;
            const uint32_t xoff = sX + wg * 16384 + tid * 16;
            uint32_t raddr;
            asm volatile("mapa.shared::cluster.u32 %0, %1, %2;" : "=r"(raddr) : "r"(xoff), "r"(crank ^ 2));
#pragma unroll
            for (int i = 0; i < 8; i++) {
                uint32_t v[4];
#pragma unroll
                for (int q = 0; q < 2; q++) {
                    const int jj = i * 2 + q;
                    float a0, a1, a2, a3;
                    if (part == 0) {
                        a0 = acc[4 * (16 + jj)]; a1 = acc[4 * (16 + jj) + 1]; a2 = acc[4 * (16 + jj) + 2]; a3 = acc[4 * (16 + jj) + 3];
                    } else {
                        a0 = acc[4 * jj]; a1 = acc[4 * jj + 1]; a2 = acc[4 * jj + 2]; a3 = acc[4 * jj + 3];
                    }
                    v[2 * q] = pack_bf16(a0, a1);
                    v[2 * q + 1] = pack_bf16(a2, a3);
                }
                asm volatile("st.shared::cluster.v4.b32 [%0], {%1, %2, %3, %4};" ::"r"(raddr + i * 2048), "r"(v[0]),
                             "r"(v[1]), "r"(v[2]), "r"(v[3]) : "memory");
            }
            cluster_arrive();
            cluster_wait();
            bf16* dst = out + (size_t)(m_tile * 128 + row0) * 2048 + n_tile * 256 + part * 128 + colq;
            const uint4* xin = reinterpret_cast<const uint4*>(sgen + (xoff - sbase));
#pragma unroll
            for (int i = 0; i < 8; i++) {
                const uint4 r = xin[i * 128];
                const uint32_t rv[4] = {r.x, r.y, r.z, r.w};
#pragma unroll
                for (int q = 0; q < 2; q++) {
                    const int jj = i * 2 + q;
                    float o0, o1, o2, o3;
                    if (part == 0) {
                        const uint32_t p0 = pack_bf16(acc[4 * jj], acc[4 * jj + 1]);
                        const uint32_t p1 = pack_bf16(acc[4 * jj + 2], acc[4 * jj + 3]);
                        o0 = bf_lo(p0) - bf_lo(rv[2 * q]);
                        o1 = bf_hi(p0) - bf_hi(rv[2 * q]);
                        o2 = bf_lo(p1) - bf_lo(rv[2 * q + 1]);
                        o3 = bf_hi(p1) - bf_hi(rv[2 * q + 1]);
                    } else {
                        const uint32_t p0 = pack_bf16(acc[4 * (16 + jj)], acc[4 * (16 + jj) + 1]);
                        const uint32_t p1 = pack_bf16(acc[4 * (16 + jj) + 2], acc[4 * (16 + jj) + 3]);
                        o0 = bf_lo(rv[2 * q]) - bf_lo(p0);
                        o1 = bf_hi(rv[2 * q]) - bf_hi(p0);
                        o2 = bf_lo(rv[2 * q + 1]) - bf_lo(p1);
                        o3 = bf_hi(rv[2 * q + 1]) - bf_hi(p1);
                    }
                    *reinterpret_cast<uint32_t*>(dst + jj * 8) = pack_bf16(o0, o1);
                    *reinterpret_cast<uint32_t*>(dst + 8 * 2048 + jj * 8) = pack_bf16(o2, o3);
                }
            }
        }
    }
    if (MODE == 0) {
        cluster_arrive();
        cluster_wait();
    }
}

__device__ __forceinline__ float bfr(float x) { return __bfloat162float(__float2bfloat16_rn(x)); }

__global__ void kv_kernel(const bf16* __restrict__ k, const bf16* __restrict__ v, const bf16* __restrict__ shift_k) {
    int idx = blockIdx.x * blockDim.x + threadIdx.x;
    int s = idx / D_DIM, d = idx % D_DIM;
    float acc = 0.f;
#pragma unroll
    for (int t = 0; t < 4; t++) {
        int ss = s - 3 + t;
        float kk = ss >= 0 ? __bfloat162float(k[ss * D_DIM + d]) : 0.f;
        float w = __bfloat162float(shift_k[d * 4 + 3 - t]);
        acc = bfr(acc + bfr(kk * w));
    }
    g_kv[idx] = __float2bfloat16_rn(acc * __bfloat162float(v[idx]));
}

__global__ void conv_naive_kernel(const bf16* __restrict__ q, const bf16* __restrict__ ssm_k,
                                  const bf16* __restrict__ ssm_D, bf16* __restrict__ out) {
    int idx = blockIdx.x * blockDim.x + threadIdx.x;
    int s = idx / D_DIM, d = idx % D_DIM;
    float acc = 0.f;
    for (int j = 0; j <= s; j++) acc += __bfloat162float(g_kv[j * D_DIM + d]) * __bfloat162float(ssm_k[d * S_LEN + s - j]);
    float y = bfr(acc);
    y = bfr(y + bfr(__bfloat162float(g_kv[idx]) * __bfloat162float(ssm_D[d])));
    out[(size_t)s * 2048 + 1024 + d] = __float2bfloat16_rn(__bfloat162float(q[idx]) * y);
}

typedef CUresult (*PFN_encodeTiled)(CUtensorMap*, CUtensorMapDataType, cuuint32_t, void*, const cuuint64_t*,
                                    const cuuint64_t*, const cuuint32_t*, const cuuint32_t*, CUtensorMapInterleave,
                                    CUtensorMapSwizzle, CUtensorMapL2promotion, CUtensorMapFloatOOBfill);

static void make_map(PFN_encodeTiled fn, CUtensorMap* m, const void* ptr, uint64_t inner, uint64_t outer,
                     uint32_t box_inner, uint32_t box_outer) {
    cuuint64_t dims[2] = {inner, outer};
    cuuint64_t strides[1] = {inner * 2};
    cuuint32_t box[2] = {box_inner, box_outer};
    cuuint32_t es[2] = {1, 1};
    fn(m, CU_TENSOR_MAP_DATA_TYPE_BFLOAT16, 2, const_cast<void*>(ptr), dims, strides, box, es,
       CU_TENSOR_MAP_INTERLEAVE_NONE, CU_TENSOR_MAP_SWIZZLE_128B, CU_TENSOR_MAP_L2_PROMOTION_L2_256B,
       CU_TENSOR_MAP_FLOAT_OOB_FILL_NONE);
}

template <typename K, typename... Args>
static void launch_cluster(K kern, int grid, int block, int smem, int cluster, cudaStream_t st, Args... args) {
    cudaLaunchConfig_t cfg = {};
    cfg.gridDim = dim3(grid);
    cfg.blockDim = dim3(block);
    cfg.dynamicSmemBytes = smem;
    cfg.stream = st;
    cudaLaunchAttribute at[1];
    at[0].id = cudaLaunchAttributeClusterDimension;
    at[0].val.clusterDim.x = cluster;
    at[0].val.clusterDim.y = 1;
    at[0].val.clusterDim.z = 1;
    cfg.attrs = at;
    cfg.numAttrs = 1;
    cudaLaunchKernelEx(&cfg, kern, args...);
}

extern "C" void kernel_launch(void* const* d_in, const int* in_sizes, int n_in, void* d_out, int out_size) {
    const bf16* x = (const bf16*)d_in[0];
    const bf16* seq_re = (const bf16*)d_in[1];
    const bf16* seq_im = (const bf16*)d_in[2];
    const bf16* hid_re = (const bf16*)d_in[3];
    const bf16* hid_im = (const bf16*)d_in[4];
    const bf16* q = (const bf16*)d_in[5];
    const bf16* k = (const bf16*)d_in[6];
    const bf16* v = (const bf16*)d_in[7];
    const bf16* shift_k = (const bf16*)d_in[8];
    const bf16* ssm_k = (const bf16*)d_in[9];
    const bf16* ssm_D = (const bf16*)d_in[10];
    bf16* out = (bf16*)d_out;

    static CUtensorMap m_x, m_wre, m_wim, m_cre, m_cim, m_ab;
    static bool init = false;
    if (!init) {
        void* fnp = nullptr;
        cudaDriverEntryPointQueryResult qres;
        cudaGetDriverEntryPoint("cuTensorMapEncodeTiled", &fnp, cudaEnableDefault, &qres);
        PFN_encodeTiled fn = (PFN_encodeTiled)fnp;
        void* abp = nullptr;
        cudaGetSymbolAddress(&abp, g_abT);
        make_map(fn, &m_x, x, 1024, 2048, 64, 128);
        make_map(fn, &m_wre, hid_re, 1024, 1024, 64, 128);
        make_map(fn, &m_wim, hid_im, 1024, 1024, 64, 128);
        make_map(fn, &m_cre, seq_re, 2048, 2048, 64, 128);
        make_map(fn, &m_cim, seq_im, 2048, 2048, 64, 128);
        make_map(fn, &m_ab, abp, 2048, 2048, 64, 128);
        cudaFuncSetAttribute(gemm_kernel<0>, cudaFuncAttributeMaxDynamicSharedMemorySize, G_SMEM_BYTES);
        cudaFuncSetAttribute(gemm_kernel<1>, cudaFuncAttributeMaxDynamicSharedMemorySize, G_SMEM_BYTES);
        init = true;
    }
    cudaStream_t st = cudaStreamPerThread;
    launch_cluster(gemm_kernel<0>, 128, 384, G_SMEM_BYTES, 2, st, m_wre, m_wim, m_x, out);
    launch_cluster(gemm_kernel<1>, 128, 384, G_SMEM_BYTES, 4, st, m_cre, m_cim, m_ab, out);
    kv_kernel<<<2048 * 1024 / 256, 256, 0, st>>>(k, v, shift_k);
    conv_naive_kernel<<<2048 * 1024 / 256, 256, 0, st>>>(q, ssm_k, ssm_D, out);
}
```

```cpp
#include <cuda_runtime.h>
#include <cuda_bf16.h>
#include <cuda.h>
#include <stdint.h>

typedef __nv_bfloat16 bf16;

constexpr int S_LEN = 2048;
constexpr int D_DIM = 1024;

__device__ bf16 g_abT[2048 * 2048];

__device__ __forceinline__ uint32_t smem_u32(const void* p) {
    return (uint32_t)__cvta_generic_to_shared(p);
}
__device__ __forceinline__ void mbar_init(uint32_t bar, uint32_t count) {
    asm volatile("mbarrier.init.shared::cta.b64 [%0], %1;" ::"r"(bar), "r"(count) : "memory");
}
__device__ __forceinline__ void mbar_expect_tx(uint32_t bar, uint32_t bytes) {
    asm volatile("mbarrier.arrive.expect_tx.shared::cta.b64 _, [%0], %1;" ::"r"(bar), "r"(bytes) : "memory");
}
__device__ __forceinline__ void mbar_arrive_local(uint32_t bar) {
    asm volatile("mbarrier.arrive.shared::cta.b64 _, [%0];" ::"r"(bar) : "memory");
}
__device__ __forceinline__ void mbar_arrive_remote(uint32_t bar, uint32_t cta) {
    asm volatile(
        "{\n"
        ".reg .b32 ra;\n"
        "mapa.shared::cluster.u32 ra, %0, %1;\n"
        "mbarrier.arrive.shared::cluster.b64 _, [ra];\n"
        "}\n" ::"r"(bar), "r"(cta) : "memory");
}
__device__ __forceinline__ void mbar_wait(uint32_t bar, uint32_t parity) {
    uint32_t done;
    int it = 0;
    do {
        asm volatile(
            "{\n"
            ".reg .pred p;\n"
            "mbarrier.try_wait.parity.shared::cta.b64 p, [%1], %2;\n"
            "selp.u32 %0, 1, 0, p;\n"
            "}\n" : "=r"(done) : "r"(bar), "r"(parity) : "memory");
        if (++it > (1 << 22)) asm volatile("trap;");
    } while (!done);
}
__device__ __forceinline__ void tma_load_2d(uint32_t dst, const CUtensorMap* map, uint32_t bar, int c0, int c1) {
    asm volatile(
        "cp.async.bulk.tensor.2d.shared::cluster.global.mbarrier::complete_tx::bytes [%0], [%1, {%3, %4}], [%2];"
        ::"r"(dst), "l"(map), "r"(bar), "r"(c0), "r"(c1) : "memory");
}
__device__ __forceinline__ void tma_load_2d_mc(uint32_t dst, const CUtensorMap* map, uint32_t bar, int c0, int c1,
                                               uint16_t mask) {
    asm volatile(
        "cp.async.bulk.tensor.2d.shared::cluster.global.mbarrier::complete_tx::bytes.multicast::cluster [%0], [%1, {%3, %4}], [%2], %5;"
        ::"r"(dst), "l"(map), "r"(bar), "r"(c0), "r"(c1), "h"(mask) : "memory");
}
__device__ __forceinline__ void tma_store_2d(const CUtensorMap* map, uint32_t src, int c0, int c1) {
    asm volatile("cp.async.bulk.tensor.2d.global.shared::cta.bulk_group [%0, {%2, %3}], [%1];"
                 ::"l"(map), "r"(src), "r"(c0), "r"(c1) : "memory");
}
__device__ __forceinline__ void stmatrix_x4(uint32_t addr, uint32_t r0, uint32_t r1, uint32_t r2, uint32_t r3) {
    asm volatile("stmatrix.sync.aligned.m8n8.x4.shared.b16 [%0], {%1, %2, %3, %4};" ::"r"(addr), "r"(r0), "r"(r1),
                 "r"(r2), "r"(r3) : "memory");
}
__device__ __forceinline__ void named_bar_sync(int id, int n) {
    asm volatile("bar.sync %0, %1;" ::"r"(id), "r"(n) : "memory");
}
__device__ __forceinline__ void cluster_arrive_relaxed() {
    asm volatile("barrier.cluster.arrive.relaxed.aligned;" ::: "memory");
}
__device__ __forceinline__ uint32_t cluster_rank() {
    uint32_t r;
    asm volatile("mov.u32 %0, %%cluster_ctarank;" : "=r"(r));
    return r;
}
__device__ __forceinline__ void cluster_arrive() {
    asm volatile("barrier.cluster.arrive.release.aligned;" ::: "memory");
}
__device__ __forceinline__ void cluster_wait() {
    asm volatile("barrier.cluster.wait.acquire.aligned;" ::: "memory");
}
__device__ __forceinline__ void wgmma_fence() { asm volatile("wgmma.fence.sync.aligned;" ::: "memory"); }
__device__ __forceinline__ void wgmma_commit() { asm volatile("wgmma.commit_group.sync.aligned;" ::: "memory"); }
template <int N>
__device__ __forceinline__ void wgmma_wait() {
    asm volatile("wgmma.wait_group.sync.aligned %0;" ::"n"(N) : "memory");
}
__device__ __forceinline__ uint64_t make_desc_sw128(uint32_t saddr) {
    uint64_t d = 0;
    d |= (uint64_t)((saddr & 0x3FFFF) >> 4);
    d |= (uint64_t)1 << 16;
    d |= (uint64_t)(1024 >> 4) << 32;
    d |= (uint64_t)1 << 62;
    return d;
}

#define ACC8(b) "+f"(acc[b + 0]), "+f"(acc[b + 1]), "+f"(acc[b + 2]), "+f"(acc[b + 3]), "+f"(acc[b + 4]), "+f"(acc[b + 5]), "+f"(acc[b + 6]), "+f"(acc[b + 7])

__device__ __forceinline__ void wgmma_m64n256k16(float (&acc)[128], uint64_t da, uint64_t db) {
    asm volatile(
        "{\n"
        ".reg .pred p;\n"
        "setp.ne.b32 p, 1, 0;\n"
        "wgmma.mma_async.sync.aligned.m64n256k16.f32.bf16.bf16 "
        "{%0, %1, %2, %3, %4, %5, %6, %7, %8, %9, %10, %11, %12, %13, %14, %15, "
        "%16, %17, %18, %19, %20, %21, %22, %23, %24, %25, %26, %27, %28, %29, %30, %31, "
        "%32, %33, %34, %35, %36, %37, %38, %39, %40, %41, %42, %43, %44, %45, %46, %47, "
        "%48, %49, %50, %51, %52, %53, %54, %55, %56, %57, %58, %59, %60, %61, %62, %63, "
        "%64, %65, %66, %67, %68, %69, %70, %71, %72, %73, %74, %75, %76, %77, %78, %79, "
        "%80, %81, %82, %83, %84, %85, %86, %87, %88, %89, %90, %91, %92, %93, %94, %95, "
        "%96, %97, %98, %99, %100, %101, %102, %103, %104, %105, %106, %107, %108, %109, %110, %111, "
        "%112, %113, %114, %115, %116, %117, %118, %119, %120, %121, %122, %123, %124, %125, %126, %127}, "
        "%128, %129, p, 1, 1, 0, 0;\n"
        "}\n"
        : ACC8(0), ACC8(8), ACC8(16), ACC8(24), ACC8(32), ACC8(40), ACC8(48), ACC8(56), ACC8(64), ACC8(72), ACC8(80),
          ACC8(88), ACC8(96), ACC8(104), ACC8(112), ACC8(120)
        : "l"(da), "l"(db));
}

__device__ __forceinline__ uint32_t pack_bf16(float lo, float hi) {
    __nv_bfloat162 v = __floats2bfloat162_rn(lo, hi);
    return *reinterpret_cast<uint32_t*>(&v);
}
__device__ __forceinline__ float bf_lo(uint32_t v) { return __uint_as_float(v << 16); }
__device__ __forceinline__ float bf_hi(uint32_t v) { return __uint_as_float(v & 0xFFFF0000u); }

constexpr int IMG_KV = 0;
constexpr int IMG_HE = (128 + 2048) * 2;
constexpr int IMG_HO = IMG_HE + 2064 * 2 + 32;
constexpr int IMG_BYTES = IMG_HO + 2064 * 2;
constexpr int GKV_BYTES = 2048 * 2;
constexpr int GKV_STRIDE = 4096 + 160;
constexpr int ZT_STRIDE = 2048 + 80;
__device__ __align__(128) bf16 g_zT[1024 * ZT_STRIDE];
__device__ __align__(128) uint8_t g_img[1024 * GKV_STRIDE];

__device__ __forceinline__ float bfr(float x) { return __bfloat162float(__float2bfloat16_rn(x)); }

#define DBG_T(i)

__device__ __forceinline__ uint2 ldg64v(const void* p) {
    uint2 r;
    asm volatile("ld.global.nc.v2.b32 {%0, %1}, [%2];" : "=r"(r.x), "=r"(r.y) : "l"(p));
    return r;
}
__device__ __forceinline__ uint4 ldg128v(const void* p) {
    uint4 r;
    asm volatile("ld.global.nc.v4.b32 {%0, %1, %2, %3}, [%4];" : "=r"(r.x), "=r"(r.y), "=r"(r.z), "=r"(r.w) : "l"(p));
    return r;
}
__device__ __forceinline__ uint4 ldcg128v(const void* p) {
    uint4 r;
    asm volatile("ld.global.cg.v4.b32 {%0, %1, %2, %3}, [%4];" : "=r"(r.x), "=r"(r.y), "=r"(r.z), "=r"(r.w) : "l"(p));
    return r;
}
constexpr int PREP_K_BYTES = 67 * 256;
constexpr int PREP_V_BYTES = 64 * 256;
__device__ __forceinline__ void conv_prep_phase(const uint8_t* ksm, const uint8_t* vsm, const uint4 (&wpre)[3][2],
                                                int ch_base, int s_base, int tid) {
#pragma unroll
    for (int rnd = 0; rnd < 3; rnd++) {
        const int it = tid + rnd * 96;
        if (it >= 256) break;
        const int cg = it >> 3, rg = it & 7;
        const int ch0 = ch_base + cg * 4;
        uint2 kr[11], vr[8];
#pragma unroll
        for (int r = 0; r < 11; r++) kr[r] = *reinterpret_cast<const uint2*>(ksm + (rg * 8 + r) * 256 + cg * 8);
#pragma unroll
        for (int r = 0; r < 8; r++) vr[r] = *reinterpret_cast<const uint2*>(vsm + (rg * 8 + r) * 256 + cg * 8);
        const uint4 wa = wpre[rnd][0], wb = wpre[rnd][1];
        uint32_t w2[2][4];
        w2[0][0] = __byte_perm(wa.x, wa.z, 0x5410); w2[0][1] = __byte_perm(wa.x, wa.z, 0x7632);
        w2[0][2] = __byte_perm(wa.y, wa.w, 0x5410); w2[0][3] = __byte_perm(wa.y, wa.w, 0x7632);
        w2[1][0] = __byte_perm(wb.x, wb.z, 0x5410); w2[1][1] = __byte_perm(wb.x, wb.z, 0x7632);
        w2[1][2] = __byte_perm(wb.y, wb.w, 0x5410); w2[1][3] = __byte_perm(wb.y, wb.w, 0x7632);
#pragma unroll
        for (int p = 0; p < 2; p++) {
            uint32_t kv2[8];
#pragma unroll
            for (int r = 0; r < 8; r++) {
                __nv_bfloat162 acc;
#pragma unroll
                for (int tt = 0; tt < 4; tt++) {
                    const uint32_t u = p ? kr[r + tt].y : kr[r + tt].x;
                    const __nv_bfloat162 pr = __hmul2_rn(*reinterpret_cast<const __nv_bfloat162*>(&u),
                                                      *reinterpret_cast<const __nv_bfloat162*>(&w2[p][3 - tt]));
                    acc = (tt == 0) ? pr : __hadd2_rn(acc, pr);
                }
                const uint32_t uv = p ? vr[r].y : vr[r].x;
                const __nv_bfloat162 o = __hmul2_rn(acc, *reinterpret_cast<const __nv_bfloat162*>(&uv));
                kv2[r] = *reinterpret_cast<const uint32_t*>(&o);
            }
            uint4 lo, hi;
            lo.x = __byte_perm(kv2[1], kv2[0], 0x5410); hi.x = __byte_perm(kv2[1], kv2[0], 0x7632);
            lo.y = __byte_perm(kv2[3], kv2[2], 0x5410); hi.y = __byte_perm(kv2[3], kv2[2], 0x7632);
            lo.z = __byte_perm(kv2[5], kv2[4], 0x5410); hi.z = __byte_perm(kv2[5], kv2[4], 0x7632);
            lo.w = __byte_perm(kv2[7], kv2[6], 0x5410); hi.w = __byte_perm(kv2[7], kv2[6], 0x7632);
            *reinterpret_cast<uint4*>(g_img + (size_t)(ch0 + 2 * p) * GKV_STRIDE + (s_base + rg * 8) * 2) = lo;
            *reinterpret_cast<uint4*>(g_img + (size_t)(ch0 + 2 * p + 1) * GKV_STRIDE + (s_base + rg * 8) * 2) = hi;
        }
    }
}

__device__ __forceinline__ void conv_post(const bf16* __restrict__ q, bf16* __restrict__ out, int b, int tid, int nthr) {
    for (int it = tid; it < 256; it += nthr) {
        const int ch0 = (it & 127) * 8;
        const int s0 = b * 16 + (it >> 7) * 8;
        uint4 yr[8], qr[8];
#pragma unroll
        for (int r = 0; r < 8; r++) qr[r] = ldg128v(q + (size_t)(s0 + r) * D_DIM + ch0);
#pragma unroll
        for (int c = 0; c < 8; c++) yr[c] = ldcg128v(g_zT + (size_t)(ch0 + c) * ZT_STRIDE + s0);
#pragma unroll
        for (int r = 0; r < 8; r++) {
            float o[8];
#pragma unroll
            for (int c = 0; c < 8; c++) {
                const uint32_t uy = (&yr[c].x)[r >> 1];
                const float y = (r & 1) ? bf_hi(uy) : bf_lo(uy);
                const uint32_t uq = (&qr[r].x)[c >> 1];
                o[c] = ((c & 1) ? bf_hi(uq) : bf_lo(uq)) * y;
            }
            uint4 ov;
            ov.x = pack_bf16(o[0], o[1]); ov.y = pack_bf16(o[2], o[3]);
            ov.z = pack_bf16(o[4], o[5]); ov.w = pack_bf16(o[6], o[7]);
            *reinterpret_cast<uint4*>(out + (size_t)(s0 + r) * 2048 + 1024 + ch0) = ov;
        }
    }
}

__device__ __forceinline__ void bulk_load(uint32_t dst, const void* src, uint32_t bytes, uint32_t bar) {
    asm volatile("cp.async.bulk.shared::cluster.global.mbarrier::complete_tx::bytes [%0], [%1], %2, [%3];" ::"r"(dst),
                 "l"(src), "r"(bytes), "r"(bar) : "memory");
}
__device__ __forceinline__ void bulk_store(void* dst, uint32_t src, uint32_t bytes) {
    asm volatile("cp.async.bulk.global.shared::cta.bulk_group [%0], [%1], %2;" ::"l"(dst), "r"(src), "r"(bytes) : "memory");
}
__device__ __forceinline__ uint32_t lds32(uint32_t a) {
    uint32_t v;
    asm volatile("ld.shared.b32 %0, [%1];" : "=r"(v) : "r"(a));
    return v;
}
__device__ __forceinline__ void lds64(uint32_t a, uint32_t& x, uint32_t& y) {
    asm volatile("ld.shared.v2.b32 {%0, %1}, [%2];" : "=r"(x), "=r"(y) : "r"(a));
}
__device__ __forceinline__ void mma16816(float (&d)[4], uint32_t a0, uint32_t a1, uint32_t a2, uint32_t a3, uint32_t b0,
                                         uint32_t b1) {
    asm volatile("mma.sync.aligned.m16n8k16.row.col.f32.bf16.bf16.f32 {%0,%1,%2,%3}, {%4,%5,%6,%7}, {%8,%9}, {%0,%1,%2,%3};"
                 : "+f"(d[0]), "+f"(d[1]), "+f"(d[2]), "+f"(d[3])
                 : "r"(a0), "r"(a1), "r"(a2), "r"(a3), "r"(b0), "r"(b1));
}

__device__ __forceinline__ void conv_channel(uint32_t img, uint32_t yb, int lane) {
    const int rl = lane >> 2, ql = lane & 3;
    const int m0 = rl - 4 * ql - 3;
    const uint32_t haddr = (rl & 1) ? (img + IMG_HE + (m0 + 16) * 2) : (img + IMG_HO + (m0 + 17) * 2);
    const uint32_t kaddr = img + IMG_KV + (128 + 16 * rl + 4 * ql) * 2;
    if (lane < 2) asm volatile("st.shared.v4.b32 [%0], {%1, %1, %1, %1};" ::"r"(img + IMG_HE + lane * 16), "r"(0u) : "memory");
    if (lane >= 16) asm volatile("st.shared.v4.b32 [%0], {%1, %1, %1, %1};" ::"r"(img + IMG_KV + (lane - 16) * 16), "r"(0u) : "memory");
    __syncwarp();
    for (int j = lane; j < 258; j += 32) {
        uint32_t e0, e1, e2, e3, prev = 0;
        asm volatile("ld.shared.v4.b32 {%0, %1, %2, %3}, [%4];" : "=r"(e0), "=r"(e1), "=r"(e2), "=r"(e3) : "r"(img + IMG_HE + j * 16));
        if (j > 0) prev = lds32(img + IMG_HE + j * 16 - 4);
        asm volatile("st.shared.v4.b32 [%0], {%1, %2, %3, %4};" ::"r"(img + IMG_HO + j * 16), "r"(__funnelshift_l(prev, e0, 16)),
                     "r"(__funnelshift_l(e0, e1, 16)), "r"(__funnelshift_l(e1, e2, 16)), "r"(__funnelshift_l(e2, e3, 16)) : "memory");
    }
    __syncwarp();
    float acc[16][4];
#pragma unroll
    for (int i = 0; i < 16; i++) { acc[i][0] = 0.f; acc[i][1] = 0.f; acc[i][2] = 0.f; acc[i][3] = 0.f; }
#pragma unroll 1
    for (int rho = 0; rho < 8; rho++) {
        uint32_t F[16][2];
#pragma unroll
        for (int j = 0; j < 16; j++) lds64(kaddr + j * 256 - rho * 32, F[j][0], F[j][1]);
#pragma unroll
        for (int a = 0; a < 8; a++) {
            const uint32_t ha = haddr + (rho + 8 * a) * 32;
            const uint32_t hb = haddr + (rho + 8 * (15 - a)) * 32;
            const uint32_t a2 = lds32(ha), a0 = lds32(ha + 4), a3 = lds32(ha + 16), a1 = lds32(ha + 20);
            const uint32_t b2 = lds32(hb), b0 = lds32(hb + 4), b3 = lds32(hb + 16), b1 = lds32(hb + 20);
#pragma unroll
            for (int nt = 15 - a; nt < 16; nt++) mma16816(acc[nt], b0, b1, b2, b3, F[nt - 15 + a][0], F[nt - 15 + a][1]);
#pragma unroll
            for (int nt = a; nt < 16; nt++) mma16816(acc[nt], a0, a1, a2, a3, F[nt - a][0], F[nt - a][1]);
        }
    }
    const int mi = lane >> 3;
#pragma unroll
    for (int p = 0; p < 8; p++) {
        const int col = 8 * (2 * p + (mi >> 1)) + (lane & 7);
        const uint32_t addr = yb + (16 * col + 8 * (mi & 1)) * 2;
        asm volatile("stmatrix.sync.aligned.m8n8.x4.trans.shared.b16 [%0], {%1, %2, %3, %4};" ::"r"(addr),
                     "r"(pack_bf16(acc[2 * p][0], acc[2 * p][1])), "r"(pack_bf16(acc[2 * p][2], acc[2 * p][3])),
                     "r"(pack_bf16(acc[2 * p + 1][0], acc[2 * p + 1][1])), "r"(pack_bf16(acc[2 * p + 1][2], acc[2 * p + 1][3]))
                     : "memory");
    }
}

constexpr int G_STAGES = 4;
constexpr int G_A_BYTES = 128 * 64 * 2;
constexpr int G_B_BYTES = 256 * 64 * 2;
constexpr int G_STAGE_BYTES = G_A_BYTES + G_B_BYTES;
constexpr int OFF_A = 0;
constexpr int OFF_B = G_STAGES * G_A_BYTES;
constexpr int OFF_IMG = OFF_B;
constexpr int OFF_Y = G_STAGES * G_STAGE_BYTES;
constexpr int OFF_BAR = OFF_Y + PREP_K_BYTES + PREP_V_BYTES;
constexpr int M_SMEM_BYTES = OFF_BAR + 256 + 1024;
constexpr int KB1 = D_DIM / 64;
constexpr int KB2 = S_LEN / 64;

__device__ uint4 g_xchg[128 * 2 * 1024];
__device__ unsigned int g_xflag[256];
__device__ unsigned int g_ready[128];
__device__ unsigned int g_cnt_prep, g_cnt_conv;
__device__ unsigned int g_ticket;
__device__ unsigned int g_launch;

__device__ __forceinline__ void l2_prefetch(const void* p, uint32_t bytes) {
    asm volatile("cp.async.bulk.prefetch.L2.global [%0], %1;" ::"l"(p), "r"(bytes) : "memory");
}
__device__ __forceinline__ void spin_ge(const unsigned int* p, unsigned int target) {
    unsigned int f;
    int it = 0;
    do {
        asm volatile("ld.acquire.gpu.global.u32 %0, [%1];" : "=r"(f) : "l"(p) : "memory");
    } while ((int)(f - target) < 0 && ++it < (1 << 24));
}

struct Maps {
    CUtensorMap wre, wim, x, abo, cre, cim, ab, out, k, v;
};

__global__ void __launch_bounds__(384, 1)
fused_kernel(const __grid_constant__ Maps maps, const bf16* __restrict__ kk, const bf16* __restrict__ vv,
             const bf16* __restrict__ qq, const bf16* __restrict__ shift_k, const bf16* __restrict__ ssm_k,
             const bf16* __restrict__ ssm_D, bf16* __restrict__ out, const bf16* maps_cre_ptr,
             const bf16* maps_cim_ptr) {
    extern __shared__ uint8_t smem_raw[];
    const uint32_t sbase = (smem_u32(smem_raw) + 1023) & ~1023u;
    uint8_t* sgen = smem_raw + (sbase - smem_u32(smem_raw));
    const uint32_t sA = sbase + OFF_A;
    const uint32_t sB = sbase + OFF_B;
    const uint32_t sBar = sbase + OFF_BAR;
    auto full_bar = [&](int s) { return sBar + 8 * s; };
    auto empty_bar = [&](int s) { return sBar + 8 * (G_STAGES + s); };
    auto img_bar = [&](int c) { return sBar + 64 + 8 * c; };
    const uint32_t bar_prep = sBar + 128;
    const uint32_t bar_ml1 = sBar + 136;
    const uint32_t bar_conv = sBar + 144;
    const uint32_t bar_stg = sBar + 152;

    const int prank = cluster_rank();
    const int cid = blockIdx.x >> 1;
    const int m_tile = (cid & 7) * 2 + prank;
    const int n1_tile = cid >> 3;
    const int n2_tile = (cid >> 3) & 3;
    const int part = cid >> 5;
    const int warp = threadIdx.x >> 5;
    const int lane = threadIdx.x & 31;
    const int d0 = blockIdx.x * 8;
    const unsigned int launch = *((volatile unsigned int*)&g_launch);

    if (threadIdx.x == 0) {
        DBG_T(0);
        for (int s = 0; s < G_STAGES; s++) {
            mbar_init(full_bar(s), 1);
            mbar_init(empty_bar(s), 4);
        }
        for (int c = 0; c < 8; c++) mbar_init(img_bar(c), 1);
        mbar_init(bar_prep, 1);
        mbar_init(bar_ml1, 2);
        mbar_init(bar_conv, 8);
        mbar_init(bar_stg, 2);
        asm volatile("fence.mbarrier_init.release.cluster;" ::: "memory");
    }
    __syncthreads();
    cluster_arrive();
    cluster_wait();

    if (warp >= 8) {
        asm volatile("setmaxnreg.dec.sync.aligned.u32 104;");
        if (warp == 8) {
            if (lane == 0) {
                {
                    const CUtensorMap* mA = (m_tile < 8) ? &maps.wre : &maps.wim;
                    const int a_row = (m_tile & 7) * 128;
                    const int b_row = n1_tile * 256 + prank * 128;
                    for (int kb = 0; kb < KB1; kb++) {
                        const int st = kb % G_STAGES;
                        mbar_wait(empty_bar(st), ((kb / G_STAGES) & 1) ^ 1);
                        mbar_expect_tx(full_bar(st), G_STAGE_BYTES);
                        tma_load_2d(sA + st * G_A_BYTES, mA, full_bar(st), kb * 64, a_row);
                        tma_load_2d_mc(sB + st * G_B_BYTES + prank * 16384, &maps.x, full_bar(st), kb * 64, b_row, (uint16_t)3);
                    }
                }
                l2_prefetch(ssm_k + (size_t)d0 * S_LEN, 32768);
                mbar_wait(bar_ml1, 0);
                for (int c = 0; c < 8; c++) {
                    mbar_expect_tx(img_bar(c), GKV_BYTES + 4096);
                    bulk_load(sbase + OFF_IMG + c * IMG_BYTES + IMG_HE + 32, ssm_k + (size_t)(d0 + c) * S_LEN, 4096, img_bar(c));
                }
                spin_ge(&g_cnt_prep, 128u * (launch + 1));
                asm volatile("fence.proxy.async;" ::: "memory");
                for (int c = 0; c < 8; c++)
                    bulk_load(sbase + OFF_IMG + c * IMG_BYTES + 256, g_img + (size_t)(d0 + c) * GKV_STRIDE, GKV_BYTES, img_bar(c));
                DBG_T(11);
                mbar_wait(bar_stg, 0);
#pragma unroll
                for (int w = 0; w < 2; w++)
#pragma unroll
                    for (int c = 0; c < 4; c++)
                        tma_store_2d(&maps.abo, sbase + w * 32768 + c * 8192, n1_tile * 256 + c * 64, m_tile * 128 + w * 64);
                asm volatile("cp.async.bulk.commit_group;" ::: "memory");
                {
                    const bf16* cbase = (const bf16*)(blockIdx.x < 64 ? maps_cre_ptr : maps_cim_ptr) + (size_t)(blockIdx.x & 63) * 32 * 2048;
                    for (int i = 0; i < 4; i++) l2_prefetch(cbase + i * 8 * 2048, 32768);
                }
                asm volatile("cp.async.bulk.wait_group 0;" ::: "memory");
                asm volatile("fence.proxy.async;" ::: "memory");
                __threadfence();
                atomicAdd(&g_ready[m_tile * 8 + n1_tile], 2u);
                {
                    const CUtensorMap* mA = (part == 0) ? &maps.cre : &maps.cim;
                    const int a_row = m_tile * 128;
                    const int e_tile = part * 8 + n2_tile * 2 + prank;
                    const int b_row = e_tile * 128;
                    for (int kb = 0; kb < KB2; kb++) {
                        const int it = KB1 + kb;
                        const int st = it % G_STAGES;
                        mbar_wait(empty_bar(st), ((it / G_STAGES) & 1) ^ 1);
                        mbar_expect_tx(full_bar(st), G_STAGE_BYTES);
                        tma_load_2d(sA + st * G_A_BYTES, mA, full_bar(st), kb * 64, a_row);
                        if ((kb & 3) == 0) {
                            spin_ge(&g_ready[e_tile * 8 + (kb >> 2)], 2 * (launch + 1));
                            asm volatile("fence.proxy.async;" ::: "memory");
                        }
                        tma_load_2d_mc(sB + st * G_B_BYTES + prank * 16384, &maps.ab, full_bar(st), kb * 64, b_row, (uint16_t)3);
                    }
                }
            }
        } else {
            const int tid = threadIdx.x - 288;
            for (int ph = 0; ph < 2; ph++) {
                const int ch_base = (blockIdx.x & 3) * 256 + ph * 128, s_base = (blockIdx.x >> 2) * 64;
                if (tid == 0) {
                    mbar_expect_tx(bar_prep, PREP_K_BYTES + PREP_V_BYTES);
                    tma_load_2d(sbase + OFF_Y, &maps.k, bar_prep, ch_base, s_base - 3);
                    tma_load_2d(sbase + OFF_Y + PREP_K_BYTES, &maps.v, bar_prep, ch_base, s_base);
                    if (ph == 0) {
                        asm volatile("cp.async.bulk.prefetch.tensor.2d.L2.global [%0, {%1, %2}];" ::"l"(&maps.k), "r"(ch_base + 128), "r"(s_base - 3) : "memory");
                        asm volatile("cp.async.bulk.prefetch.tensor.2d.L2.global [%0, {%1, %2}];" ::"l"(&maps.v), "r"(ch_base + 128), "r"(s_base) : "memory");
                    }
                }
                uint4 wpre[3][2];
#pragma unroll
                for (int rnd = 0; rnd < 3; rnd++) {
                    const int c0 = ch_base + (min(tid + rnd * 96, 255) >> 3) * 4;
                    wpre[rnd][0] = ldg128v(shift_k + c0 * 4);
                    wpre[rnd][1] = ldg128v(shift_k + c0 * 4 + 8);
                }
                mbar_wait(bar_prep, ph);
                conv_prep_phase(sgen + OFF_Y, sgen + OFF_Y + PREP_K_BYTES, wpre, ch_base, s_base, tid);
                asm volatile("fence.proxy.async.shared::cta;" ::: "memory");
                named_bar_sync(4, 96);
            }
            __threadfence();
            asm volatile("fence.proxy.async;" ::: "memory");
            named_bar_sync(4, 96);
            if (tid == 0) {
                atomicAdd(&g_cnt_prep, 1u);
                DBG_T(1);
                spin_ge(&g_cnt_conv, 128u * (launch + 1));
            }
            named_bar_sync(4, 96);
            conv_post(qq, out, blockIdx.x, tid, 96);
            if (tid == 0) DBG_T(2);
        }
    } else {
        asm volatile("setmaxnreg.inc.sync.aligned.u32 200;");
        const int wg = warp >> 2;
        const int tid = threadIdx.x & 127;
        const int srow = (warp & 3) * 16 + ((lane >> 3) & 1) * 8 + (lane & 7);
        const int schunk = lane >> 4;
        const uint32_t sO = sbase + wg * 32768;
        {
            float acc[128];
#pragma unroll
            for (int i = 0; i < 128; i++) acc[i] = 0.f;
            for (int kb = 0; kb < KB1; kb++) {
                const int st = kb % G_STAGES;
                mbar_wait(full_bar(st), (kb / G_STAGES) & 1);
                const uint64_t da = make_desc_sw128(sA + st * G_A_BYTES + wg * 8192);
                const uint64_t db = make_desc_sw128(sB + st * G_B_BYTES);
                wgmma_fence();
#pragma unroll
                for (int k = 0; k < 4; k++) wgmma_m64n256k16(acc, da + 2 * k, db + 2 * k);
                wgmma_commit();
                wgmma_wait<1>();
                if (kb > 0 && kb <= KB1 - G_STAGES && tid == 0) {
                    const int pst = (kb - 1) % G_STAGES;
                    mbar_arrive_remote(empty_bar(pst), 0);
                    mbar_arrive_remote(empty_bar(pst), 1);
                }
            }
            wgmma_wait<0>();
            if (tid == 0) mbar_arrive_local(bar_ml1);
            if (threadIdx.x == 0) DBG_T(3);
            named_bar_sync(1, 256);
#pragma unroll
            for (int j = 0; j < 32; j += 2) {
                const int c = j + schunk;
                const uint32_t addr = sO + (c >> 3) * 8192 + srow * 128 + (((c & 7) ^ (srow & 7)) << 4);
                stmatrix_x4(addr, pack_bf16(acc[4 * j], acc[4 * j + 1]), pack_bf16(acc[4 * j + 2], acc[4 * j + 3]),
                            pack_bf16(acc[4 * j + 4], acc[4 * j + 5]), pack_bf16(acc[4 * j + 6], acc[4 * j + 7]));
            }
            asm volatile("fence.proxy.async.shared::cta;" ::: "memory");
            named_bar_sync(2 + wg, 128);
            if (tid == 0) mbar_arrive_local(bar_stg);
        }
        if (threadIdx.x == 0) DBG_T(4);
        mbar_wait(img_bar(warp), 0);
        if (threadIdx.x == 0) DBG_T(5);
        conv_channel(sbase + OFF_IMG + warp * IMG_BYTES, sbase + OFF_Y + warp * 4096, lane);
        __syncwarp();
        {
            const uint4* ys = reinterpret_cast<const uint4*>(sgen + OFF_Y + warp * 4096);
            uint4* zg = reinterpret_cast<uint4*>(g_zT + (size_t)(d0 + warp) * ZT_STRIDE);
            const uint4* kvs = reinterpret_cast<const uint4*>(sgen + OFF_IMG + warp * IMG_BYTES + IMG_KV + 256);
            const __nv_bfloat162 d2 = __bfloat162bfloat162(ssm_D[d0 + warp]);
#pragma unroll
            for (int i = 0; i < 8; i++) {
                const uint4 yv = ys[i * 32 + lane], kv = kvs[i * 32 + lane];
                const uint32_t yy[4] = {yv.x, yv.y, yv.z, yv.w}, kk4[4] = {kv.x, kv.y, kv.z, kv.w};
                uint32_t zz[4];
#pragma unroll
                for (int j = 0; j < 4; j++) {
                    const uint32_t ksw = __byte_perm(kk4[j], 0, 0x1032);
                    const __nv_bfloat162 z = __hadd2_rn(*reinterpret_cast<const __nv_bfloat162*>(&yy[j]),
                                                        __hmul2_rn(*reinterpret_cast<const __nv_bfloat162*>(&ksw), d2));
                    zz[j] = *reinterpret_cast<const uint32_t*>(&z);
                }
                __stcg(zg + i * 32 + lane, make_uint4(zz[0], zz[1], zz[2], zz[3]));
            }
            __threadfence();
        }
        named_bar_sync(1, 256);
        if (threadIdx.x == 0) atomicAdd(&g_cnt_conv, 1u);
        if (threadIdx.x == 0) DBG_T(6);
        asm volatile("fence.proxy.async.shared::cta;" ::: "memory");
        named_bar_sync(2 + wg, 128);
        if (tid == 0) {
            for (int st = 0; st < G_STAGES; st++) {
                mbar_arrive_remote(empty_bar(st), 0);
                mbar_arrive_remote(empty_bar(st), 1);
            }
        }
        {
            float acc[128];
#pragma unroll
            for (int i = 0; i < 128; i++) acc[i] = 0.f;
            for (int kb = 0; kb < KB2; kb++) {
                const int it = KB1 + kb;
                const int st = it % G_STAGES;
                mbar_wait(full_bar(st), (it / G_STAGES) & 1);
                const uint64_t da = make_desc_sw128(sA + st * G_A_BYTES + wg * 8192);
                const uint64_t db = make_desc_sw128(sB + st * G_B_BYTES);
                wgmma_fence();
#pragma unroll
                for (int k = 0; k < 4; k++) wgmma_m64n256k16(acc, da + 2 * k, db + 2 * k);
                wgmma_commit();
                wgmma_wait<1>();
                if (kb > 0 && kb <= KB2 - G_STAGES && tid == 0) {
                    const int pst = (it - 1) % G_STAGES;
                    mbar_arrive_remote(empty_bar(pst), 0);
                    mbar_arrive_remote(empty_bar(pst), 1);
                }
            }
            wgmma_wait<0>();
            if (threadIdx.x == 0) DBG_T(7);
            named_bar_sync(1, 256);
            const int me = blockIdx.x, partner = blockIdx.x ^ 64;
            uint4* xo = g_xchg + (size_t)(me * 2 + wg) * 1024 + tid;
#pragma unroll
            for (int i = 0; i < 8; i++) {
                uint32_t v[4];
#pragma unroll
                for (int q = 0; q < 2; q++) {
                    const int jj = i * 2 + q;
                    float a0, a1, a2, a3;
                    if (part == 0) {
                        a0 = acc[4 * (16 + jj)]; a1 = acc[4 * (16 + jj) + 1]; a2 = acc[4 * (16 + jj) + 2]; a3 = acc[4 * (16 + jj) + 3];
                    } else {
                        a0 = acc[4 * jj]; a1 = acc[4 * jj + 1]; a2 = acc[4 * jj + 2]; a3 = acc[4 * jj + 3];
                    }
                    v[2 * q] = pack_bf16(a0, a1);
                    v[2 * q + 1] = pack_bf16(a2, a3);
                }
                __stcg(xo + i * 128, make_uint4(v[0], v[1], v[2], v[3]));
            }
            __threadfence();
            named_bar_sync(2 + wg, 128);
            if (tid == 0) {
                asm volatile("st.release.gpu.global.u32 [%0], %1;" ::"l"(g_xflag + me * 2 + wg), "r"(launch + 1) : "memory");
                spin_ge(g_xflag + partner * 2 + wg, launch + 1);
            }
            named_bar_sync(2 + wg, 128);
            const uint4* xi = g_xchg + (size_t)(partner * 2 + wg) * 1024 + tid;
            uint4 rr[8];
#pragma unroll
            for (int i = 0; i < 8; i++) rr[i] = __ldcg(xi + i * 128);
#pragma unroll
            for (int i = 0; i < 8; i++) {
                const uint32_t rv[4] = {rr[i].x, rr[i].y, rr[i].z, rr[i].w};
                uint32_t o[4];
#pragma unroll
                for (int q = 0; q < 2; q++) {
                    const int jj = i * 2 + q;
                    if (part == 0) {
                        const uint32_t p0 = pack_bf16(acc[4 * jj], acc[4 * jj + 1]);
                        const uint32_t p1 = pack_bf16(acc[4 * jj + 2], acc[4 * jj + 3]);
                        o[2 * q] = pack_bf16(bf_lo(p0) - bf_lo(rv[2 * q]), bf_hi(p0) - bf_hi(rv[2 * q]));
                        o[2 * q + 1] = pack_bf16(bf_lo(p1) - bf_lo(rv[2 * q + 1]), bf_hi(p1) - bf_hi(rv[2 * q + 1]));
                    } else {
                        const uint32_t p0 = pack_bf16(acc[4 * (16 + jj)], acc[4 * (16 + jj) + 1]);
                        const uint32_t p1 = pack_bf16(acc[4 * (16 + jj) + 2], acc[4 * (16 + jj) + 3]);
                        o[2 * q] = pack_bf16(bf_lo(rv[2 * q]) - bf_lo(p0), bf_hi(rv[2 * q]) - bf_hi(p0));
                        o[2 * q + 1] = pack_bf16(bf_lo(rv[2 * q + 1]) - bf_lo(p1), bf_hi(rv[2 * q + 1]) - bf_hi(p1));
                    }
                }
                const int c = 2 * i + schunk;
                const uint32_t addr = sO + (c >> 3) * 8192 + srow * 128 + (((c & 7) ^ (srow & 7)) << 4);
                stmatrix_x4(addr, o[0], o[1], o[2], o[3]);
            }
            asm volatile("fence.proxy.async.shared::cta;" ::: "memory");
            named_bar_sync(2 + wg, 128);
            if (tid == 0) {
#pragma unroll
                for (int c = 0; c < 2; c++)
                    tma_store_2d(&maps.out, sO + c * 8192, n2_tile * 256 + part * 128 + c * 64, m_tile * 128 + wg * 64);
                asm volatile("cp.async.bulk.commit_group;" ::: "memory");
                asm volatile("cp.async.bulk.wait_group.read 0;" ::: "memory");
            }
        }
    }
    if (threadIdx.x == 0) DBG_T(8);
    cluster_arrive_relaxed();
    cluster_wait();
    if (threadIdx.x == 0) {
        DBG_T(9);
        const unsigned int t = atomicAdd(&g_ticket, 1u);
        if (t == 128u * (launch + 1) - 1u) *((volatile unsigned int*)&g_launch) = launch + 1;
    }
}

typedef CUresult (*PFN_encodeTiled)(CUtensorMap*, CUtensorMapDataType, cuuint32_t, void*, const cuuint64_t*,
                                    const cuuint64_t*, const cuuint32_t*, const cuuint32_t*, CUtensorMapInterleave,
                                    CUtensorMapSwizzle, CUtensorMapL2promotion, CUtensorMapFloatOOBfill);

static void make_map(PFN_encodeTiled fn, CUtensorMap* m, const void* ptr, uint64_t inner, uint64_t outer,
                     uint32_t box_inner, uint32_t box_outer, bool swz = true) {
    cuuint64_t dims[2] = {inner, outer};
    cuuint64_t strides[1] = {inner * 2};
    cuuint32_t box[2] = {box_inner, box_outer};
    cuuint32_t es[2] = {1, 1};
    fn(m, CU_TENSOR_MAP_DATA_TYPE_BFLOAT16, 2, const_cast<void*>(ptr), dims, strides, box, es,
       CU_TENSOR_MAP_INTERLEAVE_NONE, swz ? CU_TENSOR_MAP_SWIZZLE_128B : CU_TENSOR_MAP_SWIZZLE_NONE, CU_TENSOR_MAP_L2_PROMOTION_L2_256B,
       CU_TENSOR_MAP_FLOAT_OOB_FILL_NONE);
}

template <typename K, typename... Args>
static void launch_cluster(K kern, int grid, int block, int smem, int cluster, cudaStream_t st, Args... args) {
    cudaLaunchConfig_t cfg = {};
    cfg.gridDim = dim3(grid);
    cfg.blockDim = dim3(block);
    cfg.dynamicSmemBytes = smem;
    cfg.stream = st;
    cudaLaunchAttribute at[1];
    at[0].id = cudaLaunchAttributeClusterDimension;
    at[0].val.clusterDim.x = cluster;
    at[0].val.clusterDim.y = 1;
    at[0].val.clusterDim.z = 1;
    cfg.attrs = at;
    cfg.numAttrs = 1;
    cudaLaunchKernelEx(&cfg, kern, args...);
}

extern "C" void kernel_launch(void* const* d_in, const int* in_sizes, int n_in, void* d_out, int out_size) {
    const bf16* x = (const bf16*)d_in[0];
    const bf16* seq_re = (const bf16*)d_in[1];
    const bf16* seq_im = (const bf16*)d_in[2];
    const bf16* hid_re = (const bf16*)d_in[3];
    const bf16* hid_im = (const bf16*)d_in[4];
    const bf16* q = (const bf16*)d_in[5];
    const bf16* k = (const bf16*)d_in[6];
    const bf16* v = (const bf16*)d_in[7];
    const bf16* shift_k = (const bf16*)d_in[8];
    const bf16* ssm_k = (const bf16*)d_in[9];
    const bf16* ssm_D = (const bf16*)d_in[10];
    bf16* out = (bf16*)d_out;

    static PFN_encodeTiled fn = nullptr;
    static void* abp = nullptr;
    if (!fn) {
        void* fnp = nullptr;
        cudaDriverEntryPointQueryResult qres;
        cudaGetDriverEntryPoint("cuTensorMapEncodeTiled", &fnp, cudaEnableDefault, &qres);
        fn = (PFN_encodeTiled)fnp;
        cudaGetSymbolAddress(&abp, g_abT);
        cudaFuncSetAttribute(fused_kernel, cudaFuncAttributeMaxDynamicSharedMemorySize, M_SMEM_BYTES);
    }
    Maps maps;
    make_map(fn, &maps.x, x, 1024, 2048, 64, 128);
    make_map(fn, &maps.wre, hid_re, 1024, 1024, 64, 128);
    make_map(fn, &maps.wim, hid_im, 1024, 1024, 64, 128);
    make_map(fn, &maps.cre, seq_re, 2048, 2048, 64, 128);
    make_map(fn, &maps.cim, seq_im, 2048, 2048, 64, 128);
    make_map(fn, &maps.ab, abp, 2048, 2048, 64, 128);
    make_map(fn, &maps.abo, abp, 2048, 2048, 64, 64);
    make_map(fn, &maps.out, out, 2048, 2048, 64, 64);
    make_map(fn, &maps.k, k, 1024, 2048, 128, 67, false);
    make_map(fn, &maps.v, v, 1024, 2048, 128, 64, false);
    launch_cluster(fused_kernel, 128, 384, M_SMEM_BYTES, 2, cudaStreamPerThread, maps, k, v, q, shift_k, ssm_k, ssm_D, out, seq_re, seq_im);
}
```
